```python
import torch

def _softmax(x, axis=-1):
    return torch.softmax(x, dim=axis)
def _gelu(x):
    return torch.nn.functional.gelu(x, approximate="tanh")
def _silu(x):
    return torch.nn.functional.silu(x)
def _sigmoid(x):
    return torch.sigmoid(x)
def _layernorm(x, axis=-1, eps=1e-5):
    m = x.mean(dim=axis, keepdim=True)
    v = x.var(dim=axis, keepdim=True, unbiased=False)
    return (x - m) / torch.sqrt(v + eps)
def _scatter_add(tgt, idx, src, axis=0):
    return tgt.clone().index_add_(axis, idx, src)
def _segment_sum(src, seg, n):
    out = torch.zeros((n,) + src.shape[1:], dtype=src.dtype)
    return out.index_add_(0, seg, src)
def _pad(x, pw):
    flat = tuple(v for pair in reversed(pw) for v in pair)
    return torch.nn.functional.pad(x, flat)

kernel_name = 'parallel_sum__ssm_conv_h3__glu_gated_reglu__prompt'

def setup_inputs():

    _w = (lambda a: (lambda t: t.to(torch.bfloat16) if t.is_floating_point() else t)(torch.as_tensor(a)))
    def _A_setup():
        B, S, D = 1, 2048, 576
        ks = 4
        return {
            "q": _w((lambda *s: torch.randn(*s, dtype=torch.bfloat16) * 0.05)(B, S, D)),
            "k": _w((lambda *s: torch.randn(*s, dtype=torch.bfloat16) * 0.2)(B, S, D)),
            "v": _w((lambda *s: torch.randn(*s, dtype=torch.bfloat16) * 0.2)(B, S, D)),
            "shift_k": _w((lambda *s: torch.randn(*s, dtype=torch.bfloat16) * 0.2)(D, ks) * 0.5),
            "ssm_k": _w((lambda *s: torch.randn(*s, dtype=torch.bfloat16) * 0.4)(D, S) * (1.0 / S ** 0.5)),
            "ssm_D": _w((lambda *s: torch.randn(*s, dtype=torch.bfloat16) * 0.2)(D)),
        }
    _A_in = _A_setup()

    def _B_setup():
        B, S, D, F = 1, 2048, 576, 4608
        return {
            "x": _w((lambda *s: torch.randn(*s, dtype=torch.bfloat16) * 0.05)(B, S, D)),
            "W_gate": _w((lambda *s: torch.randn(*s, dtype=torch.bfloat16) * 0.2)(D, F) * (2.0 / D) ** 0.5),
            "W_up": _w((lambda *s: torch.randn(*s, dtype=torch.bfloat16) * 0.2)(D, F) * (2.0 / D) ** 0.5),
            "W_down": _w((lambda *s: torch.randn(*s, dtype=torch.bfloat16) * 0.2)(F, D) * (1.0 / F) ** 0.5),
        }
    _B_in = _B_setup()

    return {
        "A_q": _A_in["q"],
        "A_k": _A_in["k"],
        "A_v": _A_in["v"],
        "A_shift_k": _A_in["shift_k"],
        "A_ssm_k": _A_in["ssm_k"],
        "A_ssm_D": _A_in["ssm_D"],
        "B_x": _B_in["x"],
        "B_W_gate": _B_in["W_gate"],
        "B_W_up": _B_in["W_up"],
        "B_W_down": _B_in["W_down"],
    }

def reference(A_q, A_k, A_v, A_shift_k, A_ssm_k, A_ssm_D, B_x, B_W_gate, B_W_up, B_W_down):
    def _A_ref(q, k, v, shift_k, ssm_k, ssm_D):
        B, S, D = q.shape
        ks = shift_k.shape[-1]
        k_pad = _pad(k, ((0, 0), (ks - 1, 0), (0, 0)))
        k_shift = torch.zeros_like(k)
        for t in range(ks):
            k_shift = k_shift + k_pad[:, t:t + S, :] * shift_k[:, ks - 1 - t][None, None, :]
        kv = k_shift * v
        L = 2 * S
        kv_pad = _pad(kv, ((0, 0), (0, S), (0, 0)))
        kf_pad = _pad(ssm_k, ((0, 0), (0, S)))
        kv_f = (lambda x, axes=(-2,-1): torch.fft.rfft2(x.float(), dim=axes))(kv_pad[:, None, :, :], axes=(1, 2))
        kf_f = (lambda x, axes=(-2,-1): torch.fft.rfft2(x.float(), dim=axes))(kf_pad[:, None, :], axes=(1, 2))
        kf_f = (lambda x, *d: x.permute(*d))(kf_f, 1, 2, 0)
        y_f = kv_f * kf_f[None, :, :, :]
        y = (lambda x, s, axes=(-2,-1): torch.fft.irfft2(x, s=s, dim=axes).to(torch.bfloat16))(y_f, (1, L), axes=(1, 2))[:, 0, :S, :]
        y = y + kv * ssm_D[None, None, :]
        return q * y

    def _B_ref(x, W_gate, W_up, W_down):
        gate = torch.einsum("bsd,df->bsf", x, W_gate)
        up = torch.einsum("bsd,df->bsf", x, W_up)
        gate = gate * (lambda x, dt: x.to(dt))(gate > 0, gate.dtype)
        h = gate * up
        return torch.einsum("bsf,fd->bsd", h, W_down)

    x = A_q
    xn = _layernorm(x, axis=-1)
    return x + _A_ref(xn, A_k, A_v, A_shift_k, A_ssm_k, A_ssm_D) + _B_ref(xn, B_W_gate, B_W_up, B_W_down)
```

```cpp
#include <cuda_runtime.h>
#include <cuda_bf16.h>
#include <cuda.h>
#include <stdint.h>
#include <type_traits>

namespace {

constexpr int SEQ = 2048;
constexpr int DM = 576;
constexpr int FF = 4608;

typedef __nv_bfloat16 bf16;

__device__ __forceinline__ uint32_t smem_u32(const void* p) { return (uint32_t)__cvta_generic_to_shared(p); }
__device__ __forceinline__ void mbar_init(uint32_t bar, uint32_t cnt) {
  asm volatile("mbarrier.init.shared::cta.b64 [%0], %1;" ::"r"(bar), "r"(cnt));
}
__device__ __forceinline__ void mbar_expect_tx(uint32_t bar, uint32_t bytes) {
  asm volatile("mbarrier.arrive.expect_tx.shared::cta.b64 _, [%0], %1;" ::"r"(bar), "r"(bytes) : "memory");
}
__device__ __forceinline__ void mbar_arrive(uint32_t bar) {
  asm volatile("mbarrier.arrive.shared::cta.b64 _, [%0];" ::"r"(bar) : "memory");
}
__device__ __forceinline__ void mbar_wait(uint32_t bar, uint32_t parity) {
  asm volatile(
      "{\n.reg .pred P1;\n"
      "LAB_WAIT:\n"
      "mbarrier.try_wait.parity.shared::cta.b64 P1, [%0], %1;\n"
      "@P1 bra DONE;\n"
      "bra LAB_WAIT;\n"
      "DONE:\n}" ::"r"(bar), "r"(parity) : "memory");
}
__device__ __forceinline__ void tma_load_2d(uint32_t dst, const CUtensorMap* map, uint32_t bar, int c0, int c1) {
  asm volatile(
      "cp.async.bulk.tensor.2d.shared::cluster.global.mbarrier::complete_tx::bytes [%0], [%1, {%3, %4}], [%2];" ::"r"(dst),
      "l"(map), "r"(bar), "r"(c0), "r"(c1)
      : "memory");
}
__device__ __forceinline__ void tma_prefetch_2d(const CUtensorMap* map, int c0, int c1) {
  asm volatile("cp.async.bulk.prefetch.tensor.2d.L2.global.tile [%0, {%1, %2}];" ::"l"(map), "r"(c0), "r"(c1) : "memory");
}
__device__ __forceinline__ void bulk_store(void* gdst, uint32_t ssrc, uint32_t bytes) {
  asm volatile("cp.async.bulk.global.shared::cta.bulk_group [%0], [%1], %2;" ::"l"(gdst), "r"(ssrc), "r"(bytes) : "memory");
}
__device__ __forceinline__ void bulk_commit() { asm volatile("cp.async.bulk.commit_group;" ::: "memory"); }
__device__ __forceinline__ void bulk_wait_all() { asm volatile("cp.async.bulk.wait_group 0;" ::: "memory"); }
__device__ __forceinline__ void fence_async_smem() { asm volatile("fence.proxy.async.shared::cta;" ::: "memory"); }
__device__ __forceinline__ void wg_fence() { asm volatile("wgmma.fence.sync.aligned;" ::: "memory"); }
__device__ __forceinline__ void wg_commit() { asm volatile("wgmma.commit_group.sync.aligned;" ::: "memory"); }
template <int N>
__device__ __forceinline__ void wg_wait() { asm volatile("wgmma.wait_group.sync.aligned %0;" ::"n"(N) : "memory"); }
__device__ __forceinline__ void ldsm_x4(uint32_t addr, uint32_t& r0, uint32_t& r1, uint32_t& r2, uint32_t& r3) {
  asm volatile("ldmatrix.sync.aligned.m8n8.x4.shared.b16 {%0, %1, %2, %3}, [%4];"
               : "=r"(r0), "=r"(r1), "=r"(r2), "=r"(r3) : "r"(addr) : "memory");
}
__device__ __forceinline__ void stsm_x4(uint32_t addr, uint32_t r0, uint32_t r1, uint32_t r2, uint32_t r3) {
  asm volatile("stmatrix.sync.aligned.m8n8.x4.shared.b16 [%0], {%1, %2, %3, %4};" ::"r"(addr), "r"(r0), "r"(r1), "r"(r2), "r"(r3)
               : "memory");
}
__device__ __forceinline__ void sts_v4(uint32_t addr, uint32_t r0, uint32_t r1, uint32_t r2, uint32_t r3) {
  asm volatile("st.shared.v4.b32 [%0], {%1, %2, %3, %4};" ::"r"(addr), "r"(r0), "r"(r1), "r"(r2), "r"(r3) : "memory");
}
__device__ __forceinline__ void lds_v4(uint32_t addr, uint32_t& r0, uint32_t& r1, uint32_t& r2, uint32_t& r3) {
  asm volatile("ld.shared.v4.b32 {%0, %1, %2, %3}, [%4];" : "=r"(r0), "=r"(r1), "=r"(r2), "=r"(r3) : "r"(addr) : "memory");
}
__device__ __forceinline__ uint32_t pack_bf16(float lo, float hi) {
  uint32_t r;
  asm("cvt.rn.bf16x2.f32 %0, %1, %2;" : "=r"(r) : "f"(hi), "f"(lo));
  return r;
}
__device__ __forceinline__ uint32_t pack_bf16_relu(float lo, float hi) {
  uint32_t r;
  asm("cvt.rn.relu.bf16x2.f32 %0, %1, %2;" : "=r"(r) : "f"(hi), "f"(lo));
  return r;
}
__device__ __forceinline__ uint32_t mul_bf16x2(uint32_t a, uint32_t b) {
  uint32_t r;
  asm("mul.rn.bf16x2 %0, %1, %2;" : "=r"(r) : "r"(a), "r"(b));
  return r;
}
__device__ __forceinline__ uint32_t add_bf16x2(uint32_t a, uint32_t b) {
  uint32_t r;
  asm("add.rn.bf16x2 %0, %1, %2;" : "=r"(r) : "r"(a), "r"(b));
  return r;
}
__device__ __forceinline__ float bf_lo(uint32_t v) { return __uint_as_float(v << 16); }
__device__ __forceinline__ float bf_hi(uint32_t v) { return __uint_as_float(v & 0xffff0000u); }
template <int N>
__device__ __forceinline__ void acc_fence(float (&d)[N]) {
#pragma unroll
  for (int i = 0; i < N; i++) asm volatile("" : "+f"(d[i])::"memory");
}
constexpr uint32_t DESC_HI_SW128 = (1024u >> 4) | (1u << 30);
constexpr uint32_t DESC_HI_SW32 = (256u >> 4) | (3u << 30);
__device__ __forceinline__ void wgmma_rs128_first(float (&d)[64], uint32_t a0, uint32_t a1, uint32_t a2, uint32_t a3, uint32_t dlo) {
  asm volatile("{\n.reg .b64 db;\nmov.b64 db, {%68, %69};\n"
    "wgmma.mma_async.sync.aligned.m64n128k16.f32.bf16.bf16 "
    "{%0, %1, %2, %3, %4, %5, %6, %7, %8, %9, %10, %11, %12, %13, %14, %15, "
    "%16, %17, %18, %19, %20, %21, %22, %23, %24, %25, %26, %27, %28, %29, %30, %31, "
    "%32, %33, %34, %35, %36, %37, %38, %39, %40, %41, %42, %43, %44, %45, %46, %47, "
    "%48, %49, %50, %51, %52, %53, %54, %55, %56, %57, %58, %59, %60, %61, %62, %63}, "
    "{%64, %65, %66, %67}, db, 0, 1, 1, 1;\n}\n"
    : "+f"(d[0]), "+f"(d[1]), "+f"(d[2]), "+f"(d[3]), "+f"(d[4]), "+f"(d[5]), "+f"(d[6]), "+f"(d[7]),
      "+f"(d[8]), "+f"(d[9]), "+f"(d[10]), "+f"(d[11]), "+f"(d[12]), "+f"(d[13]), "+f"(d[14]), "+f"(d[15]),
      "+f"(d[16]), "+f"(d[17]), "+f"(d[18]), "+f"(d[19]), "+f"(d[20]), "+f"(d[21]), "+f"(d[22]), "+f"(d[23]),
      "+f"(d[24]), "+f"(d[25]), "+f"(d[26]), "+f"(d[27]), "+f"(d[28]), "+f"(d[29]), "+f"(d[30]), "+f"(d[31]),
      "+f"(d[32]), "+f"(d[33]), "+f"(d[34]), "+f"(d[35]), "+f"(d[36]), "+f"(d[37]), "+f"(d[38]), "+f"(d[39]),
      "+f"(d[40]), "+f"(d[41]), "+f"(d[42]), "+f"(d[43]), "+f"(d[44]), "+f"(d[45]), "+f"(d[46]), "+f"(d[47]),
      "+f"(d[48]), "+f"(d[49]), "+f"(d[50]), "+f"(d[51]), "+f"(d[52]), "+f"(d[53]), "+f"(d[54]), "+f"(d[55]),
      "+f"(d[56]), "+f"(d[57]), "+f"(d[58]), "+f"(d[59]), "+f"(d[60]), "+f"(d[61]), "+f"(d[62]), "+f"(d[63])
    : "r"(a0), "r"(a1), "r"(a2), "r"(a3), "r"(dlo), "n"(DESC_HI_SW128));
}
__device__ __forceinline__ void wgmma_rs128(float (&d)[64], uint32_t a0, uint32_t a1, uint32_t a2, uint32_t a3, uint32_t dlo) {
  asm volatile("{\n.reg .b64 db;\nmov.b64 db, {%68, %69};\n"
    "wgmma.mma_async.sync.aligned.m64n128k16.f32.bf16.bf16 "
    "{%0, %1, %2, %3, %4, %5, %6, %7, %8, %9, %10, %11, %12, %13, %14, %15, "
    "%16, %17, %18, %19, %20, %21, %22, %23, %24, %25, %26, %27, %28, %29, %30, %31, "
    "%32, %33, %34, %35, %36, %37, %38, %39, %40, %41, %42, %43, %44, %45, %46, %47, "
    "%48, %49, %50, %51, %52, %53, %54, %55, %56, %57, %58, %59, %60, %61, %62, %63}, "
    "{%64, %65, %66, %67}, db, 1, 1, 1, 1;\n}\n"
    : "+f"(d[0]), "+f"(d[1]), "+f"(d[2]), "+f"(d[3]), "+f"(d[4]), "+f"(d[5]), "+f"(d[6]), "+f"(d[7]),
      "+f"(d[8]), "+f"(d[9]), "+f"(d[10]), "+f"(d[11]), "+f"(d[12]), "+f"(d[13]), "+f"(d[14]), "+f"(d[15]),
      "+f"(d[16]), "+f"(d[17]), "+f"(d[18]), "+f"(d[19]), "+f"(d[20]), "+f"(d[21]), "+f"(d[22]), "+f"(d[23]),
      "+f"(d[24]), "+f"(d[25]), "+f"(d[26]), "+f"(d[27]), "+f"(d[28]), "+f"(d[29]), "+f"(d[30]), "+f"(d[31]),
      "+f"(d[32]), "+f"(d[33]), "+f"(d[34]), "+f"(d[35]), "+f"(d[36]), "+f"(d[37]), "+f"(d[38]), "+f"(d[39]),
      "+f"(d[40]), "+f"(d[41]), "+f"(d[42]), "+f"(d[43]), "+f"(d[44]), "+f"(d[45]), "+f"(d[46]), "+f"(d[47]),
      "+f"(d[48]), "+f"(d[49]), "+f"(d[50]), "+f"(d[51]), "+f"(d[52]), "+f"(d[53]), "+f"(d[54]), "+f"(d[55]),
      "+f"(d[56]), "+f"(d[57]), "+f"(d[58]), "+f"(d[59]), "+f"(d[60]), "+f"(d[61]), "+f"(d[62]), "+f"(d[63])
    : "r"(a0), "r"(a1), "r"(a2), "r"(a3), "r"(dlo), "n"(DESC_HI_SW128));
}
__device__ __forceinline__ void wgmma_rs64_first(float (&d)[64], uint32_t a0, uint32_t a1, uint32_t a2, uint32_t a3, uint32_t dlo) {
  asm volatile("{\n.reg .b64 db;\nmov.b64 db, {%36, %37};\n"
    "wgmma.mma_async.sync.aligned.m64n64k16.f32.bf16.bf16 "
    "{%0, %1, %2, %3, %4, %5, %6, %7, %8, %9, %10, %11, %12, %13, %14, %15, "
    "%16, %17, %18, %19, %20, %21, %22, %23, %24, %25, %26, %27, %28, %29, %30, %31}, "
    "{%32, %33, %34, %35}, db, 0, 1, 1, 1;\n}\n"
    : "+f"(d[0]), "+f"(d[1]), "+f"(d[2]), "+f"(d[3]), "+f"(d[4]), "+f"(d[5]), "+f"(d[6]), "+f"(d[7]),
      "+f"(d[8]), "+f"(d[9]), "+f"(d[10]), "+f"(d[11]), "+f"(d[12]), "+f"(d[13]), "+f"(d[14]), "+f"(d[15]),
      "+f"(d[16]), "+f"(d[17]), "+f"(d[18]), "+f"(d[19]), "+f"(d[20]), "+f"(d[21]), "+f"(d[22]), "+f"(d[23]),
      "+f"(d[24]), "+f"(d[25]), "+f"(d[26]), "+f"(d[27]), "+f"(d[28]), "+f"(d[29]), "+f"(d[30]), "+f"(d[31])
    : "r"(a0), "r"(a1), "r"(a2), "r"(a3), "r"(dlo), "n"(DESC_HI_SW128));
}
__device__ __forceinline__ void wgmma_rs64(float (&d)[64], uint32_t a0, uint32_t a1, uint32_t a2, uint32_t a3, uint32_t dlo) {
  asm volatile("{\n.reg .b64 db;\nmov.b64 db, {%36, %37};\n"
    "wgmma.mma_async.sync.aligned.m64n64k16.f32.bf16.bf16 "
    "{%0, %1, %2, %3, %4, %5, %6, %7, %8, %9, %10, %11, %12, %13, %14, %15, "
    "%16, %17, %18, %19, %20, %21, %22, %23, %24, %25, %26, %27, %28, %29, %30, %31}, "
    "{%32, %33, %34, %35}, db, 1, 1, 1, 1;\n}\n"
    : "+f"(d[0]), "+f"(d[1]), "+f"(d[2]), "+f"(d[3]), "+f"(d[4]), "+f"(d[5]), "+f"(d[6]), "+f"(d[7]),
      "+f"(d[8]), "+f"(d[9]), "+f"(d[10]), "+f"(d[11]), "+f"(d[12]), "+f"(d[13]), "+f"(d[14]), "+f"(d[15]),
      "+f"(d[16]), "+f"(d[17]), "+f"(d[18]), "+f"(d[19]), "+f"(d[20]), "+f"(d[21]), "+f"(d[22]), "+f"(d[23]),
      "+f"(d[24]), "+f"(d[25]), "+f"(d[26]), "+f"(d[27]), "+f"(d[28]), "+f"(d[29]), "+f"(d[30]), "+f"(d[31])
    : "r"(a0), "r"(a1), "r"(a2), "r"(a3), "r"(dlo), "n"(DESC_HI_SW128));
}
__device__ __forceinline__ void wgmma_ss128(float (&d)[64], uint32_t alo, uint32_t dlo) {
  asm volatile("{\n.reg .b64 da, db;\nmov.b64 da, {%64, %66};\nmov.b64 db, {%65, %66};\n"
    "wgmma.mma_async.sync.aligned.m64n128k16.f32.bf16.bf16 "
    "{%0, %1, %2, %3, %4, %5, %6, %7, %8, %9, %10, %11, %12, %13, %14, %15, "
    "%16, %17, %18, %19, %20, %21, %22, %23, %24, %25, %26, %27, %28, %29, %30, %31, "
    "%32, %33, %34, %35, %36, %37, %38, %39, %40, %41, %42, %43, %44, %45, %46, %47, "
    "%48, %49, %50, %51, %52, %53, %54, %55, %56, %57, %58, %59, %60, %61, %62, %63}, "
    "da, db, 1, 1, 1, 0, 1;\n}\n"
    : "+f"(d[0]), "+f"(d[1]), "+f"(d[2]), "+f"(d[3]), "+f"(d[4]), "+f"(d[5]), "+f"(d[6]), "+f"(d[7]),
      "+f"(d[8]), "+f"(d[9]), "+f"(d[10]), "+f"(d[11]), "+f"(d[12]), "+f"(d[13]), "+f"(d[14]), "+f"(d[15]),
      "+f"(d[16]), "+f"(d[17]), "+f"(d[18]), "+f"(d[19]), "+f"(d[20]), "+f"(d[21]), "+f"(d[22]), "+f"(d[23]),
      "+f"(d[24]), "+f"(d[25]), "+f"(d[26]), "+f"(d[27]), "+f"(d[28]), "+f"(d[29]), "+f"(d[30]), "+f"(d[31]),
      "+f"(d[32]), "+f"(d[33]), "+f"(d[34]), "+f"(d[35]), "+f"(d[36]), "+f"(d[37]), "+f"(d[38]), "+f"(d[39]),
      "+f"(d[40]), "+f"(d[41]), "+f"(d[42]), "+f"(d[43]), "+f"(d[44]), "+f"(d[45]), "+f"(d[46]), "+f"(d[47]),
      "+f"(d[48]), "+f"(d[49]), "+f"(d[50]), "+f"(d[51]), "+f"(d[52]), "+f"(d[53]), "+f"(d[54]), "+f"(d[55]),
      "+f"(d[56]), "+f"(d[57]), "+f"(d[58]), "+f"(d[59]), "+f"(d[60]), "+f"(d[61]), "+f"(d[62]), "+f"(d[63])
    : "r"(alo), "r"(dlo), "n"(DESC_HI_SW128));
}
__device__ __forceinline__ void wgmma_ss64(float (&d)[64], uint32_t alo, uint32_t dlo) {
  asm volatile("{\n.reg .b64 da, db;\nmov.b64 da, {%32, %34};\nmov.b64 db, {%33, %34};\n"
    "wgmma.mma_async.sync.aligned.m64n64k16.f32.bf16.bf16 "
    "{%0, %1, %2, %3, %4, %5, %6, %7, %8, %9, %10, %11, %12, %13, %14, %15, "
    "%16, %17, %18, %19, %20, %21, %22, %23, %24, %25, %26, %27, %28, %29, %30, %31}, "
    "da, db, 1, 1, 1, 0, 1;\n}\n"
    : "+f"(d[0]), "+f"(d[1]), "+f"(d[2]), "+f"(d[3]), "+f"(d[4]), "+f"(d[5]), "+f"(d[6]), "+f"(d[7]),
      "+f"(d[8]), "+f"(d[9]), "+f"(d[10]), "+f"(d[11]), "+f"(d[12]), "+f"(d[13]), "+f"(d[14]), "+f"(d[15]),
      "+f"(d[16]), "+f"(d[17]), "+f"(d[18]), "+f"(d[19]), "+f"(d[20]), "+f"(d[21]), "+f"(d[22]), "+f"(d[23]),
      "+f"(d[24]), "+f"(d[25]), "+f"(d[26]), "+f"(d[27]), "+f"(d[28]), "+f"(d[29]), "+f"(d[30]), "+f"(d[31])
    : "r"(alo), "r"(dlo), "n"(DESC_HI_SW128));
}
template <int Q, int FIRST> __device__ __forceinline__ void wgmma_q(float (&d)[64], uint32_t a0, uint32_t a1, uint32_t a2, uint32_t a3, uint32_t dlo);
template <> __device__ __forceinline__ void wgmma_q<0, 0>(float (&d)[64], uint32_t a0, uint32_t a1, uint32_t a2, uint32_t a3, uint32_t dlo) {
  asm volatile("{\n.reg .b64 db;\nmov.b64 db, {%20, %21};\n"
    "wgmma.mma_async.sync.aligned.m64n32k16.f32.bf16.bf16 "
    "{%0, %1, %2, %3, %4, %5, %6, %7, %8, %9, %10, %11, %12, %13, %14, %15}, "
    "{%16, %17, %18, %19}, db, 1, 1, 1, 0;\n}\n"
    : "+f"(d[0]), "+f"(d[1]), "+f"(d[2]), "+f"(d[3]), "+f"(d[4]), "+f"(d[5]), "+f"(d[6]), "+f"(d[7]),
      "+f"(d[8]), "+f"(d[9]), "+f"(d[10]), "+f"(d[11]), "+f"(d[12]), "+f"(d[13]), "+f"(d[14]), "+f"(d[15])
    : "r"(a0), "r"(a1), "r"(a2), "r"(a3), "r"(dlo), "n"(DESC_HI_SW32));
}
template <> __device__ __forceinline__ void wgmma_q<0, 1>(float (&d)[64], uint32_t a0, uint32_t a1, uint32_t a2, uint32_t a3, uint32_t dlo) {
  asm volatile("{\n.reg .b64 db;\nmov.b64 db, {%20, %21};\n"
    "wgmma.mma_async.sync.aligned.m64n32k16.f32.bf16.bf16 "
    "{%0, %1, %2, %3, %4, %5, %6, %7, %8, %9, %10, %11, %12, %13, %14, %15}, "
    "{%16, %17, %18, %19}, db, 0, 1, 1, 0;\n}\n"
    : "=f"(d[0]), "=f"(d[1]), "=f"(d[2]), "=f"(d[3]), "=f"(d[4]), "=f"(d[5]), "=f"(d[6]), "=f"(d[7]),
      "=f"(d[8]), "=f"(d[9]), "=f"(d[10]), "=f"(d[11]), "=f"(d[12]), "=f"(d[13]), "=f"(d[14]), "=f"(d[15])
    : "r"(a0), "r"(a1), "r"(a2), "r"(a3), "r"(dlo), "n"(DESC_HI_SW32));
}
template <> __device__ __forceinline__ void wgmma_q<1, 0>(float (&d)[64], uint32_t a0, uint32_t a1, uint32_t a2, uint32_t a3, uint32_t dlo) {
  asm volatile("{\n.reg .b64 db;\nmov.b64 db, {%20, %21};\n"
    "wgmma.mma_async.sync.aligned.m64n32k16.f32.bf16.bf16 "
    "{%0, %1, %2, %3, %4, %5, %6, %7, %8, %9, %10, %11, %12, %13, %14, %15}, "
    "{%16, %17, %18, %19}, db, 1, 1, 1, 0;\n}\n"
    : "+f"(d[16]), "+f"(d[17]), "+f"(d[18]), "+f"(d[19]), "+f"(d[20]), "+f"(d[21]), "+f"(d[22]), "+f"(d[23]),
      "+f"(d[24]), "+f"(d[25]), "+f"(d[26]), "+f"(d[27]), "+f"(d[28]), "+f"(d[29]), "+f"(d[30]), "+f"(d[31])
    : "r"(a0), "r"(a1), "r"(a2), "r"(a3), "r"(dlo), "n"(DESC_HI_SW32));
}
template <> __device__ __forceinline__ void wgmma_q<1, 1>(float (&d)[64], uint32_t a0, uint32_t a1, uint32_t a2, uint32_t a3, uint32_t dlo) {
  asm volatile("{\n.reg .b64 db;\nmov.b64 db, {%20, %21};\n"
    "wgmma.mma_async.sync.aligned.m64n32k16.f32.bf16.bf16 "
    "{%0, %1, %2, %3, %4, %5, %6, %7, %8, %9, %10, %11, %12, %13, %14, %15}, "
    "{%16, %17, %18, %19}, db, 0, 1, 1, 0;\n}\n"
    : "=f"(d[16]), "=f"(d[17]), "=f"(d[18]), "=f"(d[19]), "=f"(d[20]), "=f"(d[21]), "=f"(d[22]), "=f"(d[23]),
      "=f"(d[24]), "=f"(d[25]), "=f"(d[26]), "=f"(d[27]), "=f"(d[28]), "=f"(d[29]), "=f"(d[30]), "=f"(d[31])
    : "r"(a0), "r"(a1), "r"(a2), "r"(a3), "r"(dlo), "n"(DESC_HI_SW32));
}
template <> __device__ __forceinline__ void wgmma_q<2, 0>(float (&d)[64], uint32_t a0, uint32_t a1, uint32_t a2, uint32_t a3, uint32_t dlo) {
  asm volatile("{\n.reg .b64 db;\nmov.b64 db, {%20, %21};\n"
    "wgmma.mma_async.sync.aligned.m64n32k16.f32.bf16.bf16 "
    "{%0, %1, %2, %3, %4, %5, %6, %7, %8, %9, %10, %11, %12, %13, %14, %15}, "
    "{%16, %17, %18, %19}, db, 1, 1, 1, 0;\n}\n"
    : "+f"(d[32]), "+f"(d[33]), "+f"(d[34]), "+f"(d[35]), "+f"(d[36]), "+f"(d[37]), "+f"(d[38]), "+f"(d[39]),
      "+f"(d[40]), "+f"(d[41]), "+f"(d[42]), "+f"(d[43]), "+f"(d[44]), "+f"(d[45]), "+f"(d[46]), "+f"(d[47])
    : "r"(a0), "r"(a1), "r"(a2), "r"(a3), "r"(dlo), "n"(DESC_HI_SW32));
}
template <> __device__ __forceinline__ void wgmma_q<2, 1>(float (&d)[64], uint32_t a0, uint32_t a1, uint32_t a2, uint32_t a3, uint32_t dlo) {
  asm volatile("{\n.reg .b64 db;\nmov.b64 db, {%20, %21};\n"
    "wgmma.mma_async.sync.aligned.m64n32k16.f32.bf16.bf16 "
    "{%0, %1, %2, %3, %4, %5, %6, %7, %8, %9, %10, %11, %12, %13, %14, %15}, "
    "{%16, %17, %18, %19}, db, 0, 1, 1, 0;\n}\n"
    : "=f"(d[32]), "=f"(d[33]), "=f"(d[34]), "=f"(d[35]), "=f"(d[36]), "=f"(d[37]), "=f"(d[38]), "=f"(d[39]),
      "=f"(d[40]), "=f"(d[41]), "=f"(d[42]), "=f"(d[43]), "=f"(d[44]), "=f"(d[45]), "=f"(d[46]), "=f"(d[47])
    : "r"(a0), "r"(a1), "r"(a2), "r"(a3), "r"(dlo), "n"(DESC_HI_SW32));
}
template <> __device__ __forceinline__ void wgmma_q<3, 0>(float (&d)[64], uint32_t a0, uint32_t a1, uint32_t a2, uint32_t a3, uint32_t dlo) {
  asm volatile("{\n.reg .b64 db;\nmov.b64 db, {%20, %21};\n"
    "wgmma.mma_async.sync.aligned.m64n32k16.f32.bf16.bf16 "
    "{%0, %1, %2, %3, %4, %5, %6, %7, %8, %9, %10, %11, %12, %13, %14, %15}, "
    "{%16, %17, %18, %19}, db, 1, 1, 1, 0;\n}\n"
    : "+f"(d[48]), "+f"(d[49]), "+f"(d[50]), "+f"(d[51]), "+f"(d[52]), "+f"(d[53]), "+f"(d[54]), "+f"(d[55]),
      "+f"(d[56]), "+f"(d[57]), "+f"(d[58]), "+f"(d[59]), "+f"(d[60]), "+f"(d[61]), "+f"(d[62]), "+f"(d[63])
    : "r"(a0), "r"(a1), "r"(a2), "r"(a3), "r"(dlo), "n"(DESC_HI_SW32));
}
template <> __device__ __forceinline__ void wgmma_q<3, 1>(float (&d)[64], uint32_t a0, uint32_t a1, uint32_t a2, uint32_t a3, uint32_t dlo) {
  asm volatile("{\n.reg .b64 db;\nmov.b64 db, {%20, %21};\n"
    "wgmma.mma_async.sync.aligned.m64n32k16.f32.bf16.bf16 "
    "{%0, %1, %2, %3, %4, %5, %6, %7, %8, %9, %10, %11, %12, %13, %14, %15}, "
    "{%16, %17, %18, %19}, db, 0, 1, 1, 0;\n}\n"
    : "=f"(d[48]), "=f"(d[49]), "=f"(d[50]), "=f"(d[51]), "=f"(d[52]), "=f"(d[53]), "=f"(d[54]), "=f"(d[55]),
      "=f"(d[56]), "=f"(d[57]), "=f"(d[58]), "=f"(d[59]), "=f"(d[60]), "=f"(d[61]), "=f"(d[62]), "=f"(d[63])
    : "r"(a0), "r"(a1), "r"(a2), "r"(a3), "r"(dlo), "n"(DESC_HI_SW32));
}

__device__ uint4 g_z[DM * SEQ / 8];
__device__ uint4 g_part[16 * 8 * 8 * 9 * 128];
__device__ unsigned int g_flag[2 * 16 * 8];
__device__ uint4 g_us[DM * SEQ / 8];
__device__ unsigned int g_u_done;
__device__ unsigned int g_u_seen;
#define PROF(i)

constexpr int NST = 5;
#define XW0 1
#define XW1 2
constexpr int STAGE_BYTES = 16384;
constexpr int H_BYTES = 9 * 16384;
constexpr int BAR_OFF = H_BYTES + NST * STAGE_BYTES;
constexpr int SMEM_BYTES = BAR_OFF + 512;
constexpr int B_FULL = 0, B_EMPTY = NST, B_X = 2 * NST  , B_HFREE = B_X + 3, B_STAGED = B_HFREE + 1, B_SFREE = B_STAGED + 1,
              B_TAB = B_SFREE + 1  , B_RECV = B_TAB + 4  , B_RFREE = B_RECV + 2, B_GO = B_RFREE + 1, B_COUNT = B_GO + 1;
constexpr int STATS_OFF = BAR_OFF + 256;
constexpr int CONV_U_BYTES = 256 + 4096;
constexpr int CONV_CH_BYTES = 12800;
constexpr int CONV_D_OFF = 12672;
constexpr int CONV_OFF = 0;
constexpr int STG_OFF = 6 * 16384;
constexpr int RECV_OFF = 5 * 16384;
constexpr int PART_BYTES = 9 * 2048;
constexpr int CONV_X_OFF = CONV_OFF + 4 * CONV_CH_BYTES;
constexpr int CONV_Z_OFF = CONV_X_OFF + 2 * 8192;
static_assert(CONV_Z_OFF + 2 * 4096 <= RECV_OFF, "conv area overflows");
constexpr int CONV_X_OFF_SP = 16 * CONV_CH_BYTES, CONV_Z_OFF_SP = CONV_X_OFF_SP + 2 * 8192;
static_assert(CONV_Z_OFF_SP + 2 * 4096 <= BAR_OFF, "spare conv area overflows");
static_assert(RECV_OFF + 8 * PART_BYTES == BAR_OFF, "receive area");
constexpr int NCONV_CTA = 132;

__device__ __forceinline__ void tma_load_3d(uint32_t dst, const CUtensorMap* map, uint32_t bar, int c0, int c1, int c2) {
  asm volatile(
      "cp.async.bulk.tensor.3d.shared::cluster.global.mbarrier::complete_tx::bytes [%0], [%1, {%3, %4, %5}], [%2];" ::"r"(dst),
      "l"(map), "r"(bar), "r"(c0), "r"(c1), "r"(c2)
      : "memory");
}
__device__ __forceinline__ uint32_t lds_b32(uint32_t addr) {
  uint32_t r;
  asm volatile("ld.shared.b32 %0, [%1];" : "=r"(r) : "r"(addr) : "memory");
  return r;
}
__device__ __forceinline__ void ldsm_x4_t(uint32_t addr, uint32_t& r0, uint32_t& r1, uint32_t& r2, uint32_t& r3) {
  asm volatile("ldmatrix.sync.aligned.m8n8.x4.trans.shared.b16 {%0, %1, %2, %3}, [%4];"
               : "=r"(r0), "=r"(r1), "=r"(r2), "=r"(r3) : "r"(addr) : "memory");
}
__device__ __forceinline__ void stsm_x4_t(uint32_t addr, uint32_t r0, uint32_t r1, uint32_t r2, uint32_t r3) {
  asm volatile("stmatrix.sync.aligned.m8n8.x4.trans.shared.b16 [%0], {%1, %2, %3, %4};" ::"r"(addr), "r"(r0), "r"(r1), "r"(r2), "r"(r3)
               : "memory");
}
__device__ __forceinline__ void named_bar(int id, int n) { asm volatile("bar.sync %0, %1;" ::"r"(id), "r"(n) : "memory"); }
__device__ __forceinline__ uint32_t sub_bf16x2(uint32_t a, uint32_t b) {
  uint32_t r;
  asm("sub.rn.bf16x2 %0, %1, %2;" : "=r"(r) : "r"(a), "r"(b));
  return r;
}
__device__ __forceinline__ void ln_apply(uint32_t& x, uint32_t mu2, uint32_t rh2, uint32_t rl2) {
  asm volatile(
      "{\n.reg .b32 d, t;\n"
      "sub.rn.bf16x2 d, %0, %1;\n"
      "mul.rn.bf16x2 t, d, %3;\n"
      "fma.rn.bf16x2 %0, d, %2, t;\n}"
      : "+r"(x) : "r"(mu2), "r"(rh2), "r"(rl2));
}
__device__ __forceinline__ void ln_stat(uint32_t x, float p, float& s1, float& s2) {
  asm volatile(
      "{\n.reg .b32 lo, hi;\n.reg .f32 d0, d1;\n"
      "shl.b32 lo, %2, 16;\nand.b32 hi, %2, 0xffff0000;\n"
      "sub.rn.f32 d0, lo, %3;\nsub.rn.f32 d1, hi, %3;\n"
      "add.rn.f32 %0, %0, d0;\nfma.rn.f32 %1, d0, d0, %1;\n"
      "add.rn.f32 %0, %0, d1;\nfma.rn.f32 %1, d1, d1, %1;\n}"
      : "+f"(s1), "+f"(s2) : "r"(x), "f"(p));
}
__device__ __forceinline__ void mma16816(float (&c)[4], uint32_t a0, uint32_t a1, uint32_t a2, uint32_t a3, uint32_t b0, uint32_t b1) {
  asm volatile("mma.sync.aligned.m16n8k16.row.col.f32.bf16.bf16.f32 {%0,%1,%2,%3}, {%4,%5,%6,%7}, {%8,%9}, {%0,%1,%2,%3};"
               : "+f"(c[0]), "+f"(c[1]), "+f"(c[2]), "+f"(c[3]) : "r"(a0), "r"(a1), "r"(a2), "r"(a3), "r"(b0), "r"(b1));
}
__device__ __forceinline__ float fast_sqrt(float x) { float r; asm("sqrt.approx.f32 %0, %1;" : "=f"(r) : "f"(x)); return r; }
__device__ __forceinline__ float fast_rcp(float x) { float r; asm("rcp.approx.f32 %0, %1;" : "=f"(r) : "f"(x)); return r; }
__device__ __forceinline__ float rbf(float x) { return __bfloat162float(__float2bfloat16_rn(x)); }
__device__ __forceinline__ void mbar_wait_long(uint32_t bar, uint32_t parity) {
  asm volatile(
      "{\n.reg .pred P1;\n"
      "LAB_WAIT:\n"
      "mbarrier.try_wait.parity.shared::cta.b64 P1, [%0], %1, %2;\n"
      "@P1 bra DONE;\n"
      "bra LAB_WAIT;\n"
      "DONE:\n}" ::"r"(bar), "r"(parity), "r"(20000) : "memory");
}
__device__ __forceinline__ void spin_ge(const unsigned int* p, unsigned int target) {
  unsigned int v;
  int it = 0;
  do {
    asm volatile("ld.acquire.gpu.global.u32 %0, [%1];" : "=r"(v) : "l"(p) : "memory");
    if (v >= target) break;
    __nanosleep(64);
  } while (++it < (1 << 22));
}

__device__ __forceinline__ void conv_make_u(int tid, int blk, const bf16* __restrict__ k, const bf16* __restrict__ v,
                                            const bf16* __restrict__ shift_k) {
  const int t0 = blk * 16;
  const int sw = (blk >> 2) & 1;
#pragma unroll 1
  for (int wd = tid; wd < DM / 2; wd += 64) {
    const uint4 c = __ldg(reinterpret_cast<const uint4*>(shift_k) + wd);
    const uint32_t w0 = __byte_perm(c.x, c.z, 0x5410), w1 = __byte_perm(c.x, c.z, 0x7632);
    const uint32_t w2 = __byte_perm(c.y, c.w, 0x5410), w3 = __byte_perm(c.y, c.w, 0x7632);
    const uint32_t* kp = reinterpret_cast<const uint32_t*>(k) + (size_t)t0 * (DM / 2) + wd;
    const uint32_t* vp = reinterpret_cast<const uint32_t*>(v) + (size_t)t0 * (DM / 2) + wd;
    uint4* up = g_us + (size_t)(2 * wd) * (SEQ / 8) + blk * 2;
#pragma unroll 1
    for (int hf = 0; hf < 2; hf++) {
      uint32_t kr[11], vr[8];
      const uint32_t* kq = kp + hf * 8 * (DM / 2);
      const uint32_t* vq = vp + hf * 8 * (DM / 2);
#pragma unroll
      for (int i = 0; i < 8; i++) kr[3 + i] = __ldg(kq + i * (DM / 2));
#pragma unroll
      for (int i = 0; i < 8; i++) vr[i] = __ldg(vq + i * (DM / 2));
      kr[0] = kr[1] = kr[2] = 0u;
      if (t0 + hf > 0) {
#pragma unroll
        for (int i = 0; i < 3; i++) kr[i] = __ldg(kq + (i - 3) * (DM / 2));
      }
#pragma unroll
      for (int i = 0; i < 8; i++) {
        uint32_t a = mul_bf16x2(kr[i], w3);
        a = add_bf16x2(a, mul_bf16x2(kr[i + 1], w2));
        a = add_bf16x2(a, mul_bf16x2(kr[i + 2], w1));
        a = add_bf16x2(a, mul_bf16x2(kr[i + 3], w0));
        vr[i] = mul_bf16x2(a, vr[i]);
      }
      up[hf ^ sw] = make_uint4(__byte_perm(vr[0], vr[1], 0x5410), __byte_perm(vr[2], vr[3], 0x5410), __byte_perm(vr[4], vr[5], 0x5410),
                               __byte_perm(vr[6], vr[7], 0x5410));
      up[SEQ / 8 + (hf ^ sw)] = make_uint4(__byte_perm(vr[0], vr[1], 0x7632), __byte_perm(vr[2], vr[3], 0x7632),
                                           __byte_perm(vr[4], vr[5], 0x7632), __byte_perm(vr[6], vr[7], 0x7632));
    }
  }
}
__device__ __forceinline__ void conv_make_g(uint32_t tb, int tid, int d0, const bf16* __restrict__ ssm_k,
                                            const bf16* __restrict__ ssm_D) {
  if (tid < 4) {
    const uint32_t dd = __bfloat16_as_ushort(ssm_D[d0 + tid]);
    asm volatile("st.shared.b32 [%0], %1;" ::"r"(tb + tid * CONV_CH_BYTES + CONV_D_OFF), "r"(dd | (dd << 16)) : "memory");
  }
  const uint4* kp = reinterpret_cast<const uint4*>(ssm_k + (size_t)d0 * SEQ);
#pragma unroll 1
  for (int it = 0; it < 4; it++) {
    uint4 kv[4];
    uint32_t prev[4];
    const uint4* kq = kp + it * 256 + tid;
#pragma unroll
    for (int i = 0; i < 4; i++) kv[i] = __ldg(kq + i * 64);
    prev[0] = 0u;
    if (tid) prev[0] = __ldg(reinterpret_cast<const unsigned short*>(kq) - 1);
#pragma unroll
    for (int i = 1; i < 4; i++) prev[i] = __ldg(reinterpret_cast<const unsigned short*>(kq + i * 64) - 1);
#pragma unroll
    for (int i = 0; i < 4; i++) {
      const uint32_t gb = tb + it * CONV_CH_BYTES + CONV_U_BYTES + 64 + (i * 64 + tid) * 32;
      sts_v4(gb, __byte_perm(kv[i].x, prev[i], 0x5410), __byte_perm(kv[i].x, kv[i].x, 0x1032), __byte_perm(kv[i].y, kv[i].x, 0x7610),
             __byte_perm(kv[i].y, kv[i].y, 0x1032));
      sts_v4(gb + 16, __byte_perm(kv[i].z, kv[i].y, 0x7610), __byte_perm(kv[i].z, kv[i].z, 0x1032), __byte_perm(kv[i].w, kv[i].z, 0x7610),
             __byte_perm(kv[i].w, kv[i].w, 0x1032));
    }
  }
  if (tid < 16) sts_v4(tb + (tid >> 2) * CONV_CH_BYTES + CONV_U_BYTES + (tid & 3) * 16, 0u, 0u, 0u, 0u);
  sts_v4(tb + (tid >> 4) * CONV_CH_BYTES + (tid & 15) * 16, 0u, 0u, 0u, 0u);
}

template <int GM>
__device__ __forceinline__ void conv_ldA(uint32_t (&t)[64], uint32_t ga) {
#pragma unroll
  for (int i = 0; i < 4; i++) {
    const int L = 4 * GM + i;
    const int off = (L & 7) * 64 + (L >> 3) * 2048;
    t[4 * (L & 15) + 0] = lds_b32(ga + off);
    t[4 * (L & 15) + 1] = lds_b32(ga + off + 1024);
    t[4 * (L & 15) + 2] = lds_b32(ga + off - 32);
    t[4 * (L & 15) + 3] = lds_b32(ga + off + 992);
  }
}
template <int L, int Q>
__device__ __forceinline__ void conv_q(float (&acc)[64], const uint32_t (&t)[64], uint32_t desc) {
  if constexpr (Q >= L / 8) {
    constexpr int beta = (L & 7) + 32 * (L >> 3);
    wgmma_q<Q, L == 0>(acc, t[4 * (L & 15)], t[4 * (L & 15) + 1], t[4 * (L & 15) + 2], t[4 * (L & 15) + 3], desc + (32 * Q - beta + 8) * 2);
  }
}
template <int GM, int Q>
__device__ __forceinline__ void conv_quarter(float (&acc)[64], const uint32_t (&t)[64], uint32_t desc) {
  conv_q<4 * GM + 0, Q>(acc, t, desc);
  conv_q<4 * GM + 1, Q>(acc, t, desc);
  conv_q<4 * GM + 2, Q>(acc, t, desc);
  conv_q<4 * GM + 3, Q>(acc, t, desc);
}
template <int GM>
struct ConvLoop {
  static __device__ __forceinline__ void run(float (&acc)[64], uint32_t (&t)[64], uint32_t ga, uint32_t desc) {
    if constexpr (GM + 1 < 8) {
      if constexpr (GM >= 3) wg_wait<2>();
      conv_ldA<GM + 1>(t, ga);
    }
    wg_fence();
    conv_quarter<GM, 3>(acc, t, desc);
    conv_quarter<GM, 2>(acc, t, desc);
    conv_quarter<GM, 1>(acc, t, desc);
    conv_quarter<GM, 0>(acc, t, desc);
    wg_commit();
    ConvLoop<GM + 1>::run(acc, t, ga, desc);
  }
};
template <>
struct ConvLoop<8> {
  static __device__ __forceinline__ void run(float (&)[64], uint32_t (&)[64], uint32_t, uint32_t) {}
};

__device__ __forceinline__ void conv_channel(float (&acc)[64], uint32_t cb, uint32_t xb, uint32_t zb, int w, int lane,
                                             int barid, int d, int pb) {
  const int g = lane >> 2, q = lane & 3;
  const int w2 = w >> 1, r8 = w & 1;
  const uint32_t ga = cb + CONV_U_BYTES + (16 + 128 * w2 + 8 * r8 + g - 2 * q) * 4;
  const uint32_t desc = ((cb & 0x3FFFF) >> 4) | (1u << 16);
  uint32_t t[64];
  conv_ldA<0>(t, ga);
  if (pb) PROF(pb);
  ConvLoop<0>::run(acc, t, ga, desc);
  wg_wait<0>();
  acc_fence(acc);
  if (pb) PROF(pb + 1);
#pragma unroll
  for (int jt = 15; jt >= 2; jt--) {
    acc[4 * jt + 0] += acc[4 * (jt - 2) + 2];
    acc[4 * jt + 1] += acc[4 * (jt - 2) + 3];
  }
  const uint32_t xs = xb + r8 * 4096 + lane * 16;
  float y[16];
  if (w2 == 0) {
#pragma unroll
    for (int i = 0; i < 4; i++)
      sts_v4(xs + i * 512, __float_as_uint(acc[4 * (8 + 2 * i)]), __float_as_uint(acc[4 * (8 + 2 * i) + 1]),
             __float_as_uint(acc[4 * (9 + 2 * i)]), __float_as_uint(acc[4 * (9 + 2 * i) + 1]));
  } else {
#pragma unroll
    for (int i = 0; i < 4; i++)
      sts_v4(xs + 2048 + i * 512, __float_as_uint(acc[4 * (2 * i)]), __float_as_uint(acc[4 * (2 * i) + 1]),
             __float_as_uint(acc[4 * (2 * i + 1)]), __float_as_uint(acc[4 * (2 * i + 1) + 1]));
  }
  named_bar(barid, 128);
  {
    uint32_t r[16];
#pragma unroll
    for (int i = 0; i < 4; i++) lds_v4(xs + (w2 ? 0 : 2048) + i * 512, r[4 * i], r[4 * i + 1], r[4 * i + 2], r[4 * i + 3]);
    if (w2 == 0) {
      y[0] = acc[0]; y[1] = acc[1];
#pragma unroll
      for (int kx = 1; kx < 8; kx++) {
        y[2 * kx] = acc[4 * kx] + __uint_as_float(r[2 * (kx - 1)]);
        y[2 * kx + 1] = acc[4 * kx + 1] + __uint_as_float(r[2 * (kx - 1) + 1]);
      }
    } else {
#pragma unroll
      for (int kx = 0; kx < 8; kx++) {
        y[2 * kx] = acc[4 * (7 + kx)] + __uint_as_float(r[2 * kx]);
        y[2 * kx + 1] = acc[4 * (7 + kx) + 1] + __uint_as_float(r[2 * kx + 1]);
      }
    }
  }
  const uint32_t dd2 = lds_b32(cb + CONV_D_OFF);
#pragma unroll
  for (int kk = 0; kk < 2; kk++) {
    const int a0 = 8 * (8 * w2 + 4 * kk + (lane >> 3)) + (lane & 7);
    uint32_t u[4];
    ldsm_x4_t(cb + (a0 + 8) * 32 + ((r8 ^ ((a0 >> 2) & 1)) << 4), u[0], u[1], u[2], u[3]);
    uint32_t z[4];
#pragma unroll
    for (int i = 0; i < 4; i++) z[i] = add_bf16x2(pack_bf16(y[8 * kk + 2 * i], y[8 * kk + 2 * i + 1]), mul_bf16x2(u[i], dd2));
    stsm_x4_t(zb + a0 * 32 + r8 * 16, z[0], z[1], z[2], z[3]);
  }
  named_bar(barid, 128);
  {
    uint32_t a, b, c, d4;
    const int wt = w * 32 + lane;
    uint4* zp = g_z + (wt >> 1) * (DM * 2) + d * 2 + (wt & 1);
    lds_v4(zb + wt * 16, a, b, c, d4);
    __stcg(zp, make_uint4(~a, ~b, ~c, ~d4));
    lds_v4(zb + 2048 + wt * 16, a, b, c, d4);
    __stcg(zp + 64 * (DM * 2), make_uint4(~a, ~b, ~c, ~d4));
  }
  if (pb) PROF(pb + 2);
}

__global__ void __launch_bounds__(384, 1)
fused_kernel(const __grid_constant__ CUtensorMap map_x, const __grid_constant__ CUtensorMap map_wg,
             const __grid_constant__ CUtensorMap map_wu, const __grid_constant__ CUtensorMap map_wd, const bf16* __restrict__ x,
             const bf16* __restrict__ kin, const bf16* __restrict__ vin, const bf16* __restrict__ shift_k,
             const bf16* __restrict__ ssm_k, const bf16* __restrict__ ssm_D, bf16* __restrict__ out) {
  extern __shared__ __align__(1024) uint8_t smem[];
  const uint32_t sbase = smem_u32(smem);
  const uint32_t sH = sbase;
  const uint32_t sST = sbase + H_BYTES;
  const uint32_t bars = sbase + BAR_OFF;
  const bool is_ffn = blockIdx.x < 128;
  const int m = blockIdx.x >> 3, j = blockIdx.x & 7;
  const int warp = __shfl_sync(0xffffffffu, threadIdx.x >> 5, 0), lane = threadIdx.x & 31;
  const int ngrp = is_ffn ? 1 : 4;
  const int grp0 = is_ffn ? blockIdx.x : 128 + (blockIdx.x - 128) * 4;

  if (lane == 0) {
    if (warp == 0) {
#pragma unroll
      for (int i = 0; i < 3; i++) mbar_init(bars + 8 * (B_X + i), 1);
      asm volatile("fence.mbarrier_init.release.cluster;" ::: "memory");
      if (is_ffn) {
#pragma unroll
        for (int i = 0; i < 3; i++) {
          mbar_expect_tx(bars + 8 * (B_X + i), 3 * 16384);
          tma_load_3d(sH + i * 3 * 16384, &map_x, bars + 8 * (B_X + i), 0, m * 128, i * 3);
        }
      }
    } else if (warp == 1) {
#pragma unroll
      for (int b = 0; b < NST; b++) { mbar_init(bars + 8 * (B_FULL + b), 1); mbar_init(bars + 8 * (B_EMPTY + b), 8); }
      asm volatile("fence.mbarrier_init.release.cluster;" ::: "memory");
    } else if (warp == 2) {
      mbar_init(bars + 8 * B_HFREE, 8);
      mbar_init(bars + 8 * B_STAGED, 8);
      mbar_init(bars + 8 * B_SFREE, 1);
#pragma unroll
      for (int i = 0; i < 4; i++) mbar_init(bars + 8 * (B_TAB + i), 3);
      mbar_init(bars + 8 * B_RECV, 1);
      mbar_init(bars + 8 * (B_RECV + 1), 1);
      mbar_init(bars + 8 * B_RFREE, 1);
      mbar_init(bars + 8 * B_GO, 8);
      asm volatile("fence.mbarrier_init.release.cluster;" ::: "memory");
    }
  }
  __syncthreads();

  if (warp < 4) {
    asm volatile("setmaxnreg.dec.sync.aligned.u32 56;\n");
    if (warp == 0) {
      if (lane == 0 && is_ffn) {
        PROF(0);
        int s = 0;
        uint32_t ph = 1;
        auto prefetch_unit = [&](int u) {
          if (u < 9) {
            for (int b = m; b < 18; b += 16) tma_prefetch_2d((b & 1) ? &map_wu : &map_wg, j * 576 + u * 64, (b >> 1) * 64);
          } else if (u < 14) {
            for (int b = m; b < (u < 13 ? 18 : 9); b += 16)
              tma_prefetch_2d(&map_wd, (u - 9) * 128 + (u < 13 ? (b & 1) * 64 : 0), j * 576 + (u < 13 ? (b >> 1) : b) * 64);
          }
        };
#pragma unroll 1
        for (int c = 0; c < 9; c++) {
          if (c > 0) prefetch_unit(c + 2);
#pragma unroll 1
          for (int kb = 0; kb < 9; kb++) {
            if (c == 0 && kb < NST) mbar_wait(bars + 8 * (B_X + (kb < XW0 ? 0 : (kb < XW1 ? 1 : 2))), 0);
            mbar_wait(bars + 8 * (B_EMPTY + s), ph);
            mbar_expect_tx(bars + 8 * (B_FULL + s), 16384);
            tma_load_2d(sST + s * STAGE_BYTES, &map_wg, bars + 8 * (B_FULL + s), j * 576 + c * 64, kb * 64);
            tma_load_2d(sST + s * STAGE_BYTES + 8192, &map_wu, bars + 8 * (B_FULL + s), j * 576 + c * 64, kb * 64);
            if (c == 0 && kb == NST - 1) { prefetch_unit(1); prefetch_unit(2); }
            if (++s == NST) { s = 0; ph ^= 1; }
          }
        }
#pragma unroll 1
        for (int p = 0; p < 4; p++) {
          prefetch_unit(p + 11);
#pragma unroll 1
          for (int kb = 0; kb < 9; kb++) {
            mbar_wait(bars + 8 * (B_EMPTY + s), ph);
            mbar_expect_tx(bars + 8 * (B_FULL + s), 16384);
            tma_load_2d(sST + s * STAGE_BYTES, &map_wd, bars + 8 * (B_FULL + s), p * 128, j * 576 + kb * 64);
            tma_load_2d(sST + s * STAGE_BYTES + 8192, &map_wd, bars + 8 * (B_FULL + s), p * 128 + 64, j * 576 + kb * 64);
            if (++s == NST) { s = 0; ph ^= 1; }
          }
        }
#pragma unroll 1
        for (int kp = 0; kp < 5; kp++) {
          mbar_wait(bars + 8 * (B_EMPTY + s), ph);
          mbar_expect_tx(bars + 8 * (B_FULL + s), kp < 4 ? 16384 : 8192);
          tma_load_2d(sST + s * STAGE_BYTES, &map_wd, bars + 8 * (B_FULL + s), 512, j * 576 + kp * 128);
          if (kp < 4) tma_load_2d(sST + s * STAGE_BYTES + 8192, &map_wd, bars + 8 * (B_FULL + s), 512, j * 576 + kp * 128 + 64);
          if (++s == NST) { s = 0; ph ^= 1; }
        }
      }
    } else if (warp == 1) {
      if (lane == 0 && is_ffn) {
        uint8_t* gp = reinterpret_cast<uint8_t*>(g_part) + (size_t)(m * 64 + j) * PART_BYTES;
        const uint8_t* rp = reinterpret_cast<const uint8_t*>(g_part) + (size_t)(m * 8 + j) * 8 * PART_BYTES;
#pragma unroll 1
        for (int p = 0; p < 5; p++) {
          mbar_wait_long(bars + 8 * B_STAGED, p & 1);
          if (p == 3)
            asm volatile("cp.async.bulk.prefetch.L2.global [%0], %1;" ::"l"(x + (size_t)(m * 128 + j * 16) * DM), "r"(16 * DM * 2) : "memory");
          const int nsub = p < 4 ? 2 : 1;
#pragma unroll 1
          for (int cw = 0; cw < 8; cw++)
            for (int sb = 0; sb < nsub; sb++)
              bulk_store(gp + (size_t)cw * (8 * PART_BYTES) + (p * 2 + sb) * 2048, sH + STG_OFF + sb * 16384 + cw * 2048, 2048);
          bulk_commit();
          asm volatile("cp.async.bulk.wait_group.read 0;" ::: "memory");
          mbar_arrive(bars + 8 * B_SFREE);
          if (p >= 3) {
            if (p == 4) mbar_arrive(bars + 8 * B_RFREE);
            bulk_wait_all();
            asm volatile("fence.proxy.async.global;" ::: "memory");
            asm volatile("fence.acq_rel.gpu;" ::: "memory");
#pragma unroll 1
            for (int cw = 0; cw < 8; cw++)
              asm volatile("red.relaxed.gpu.global.add.u32 [%0], 1;" ::"l"(&g_flag[(p - 3) * 128 + m * 8 + cw]) : "memory");
          }
        }
        PROF(20);
        spin_ge(&g_flag[128 + m * 8 + j], 8);
        g_flag[128 + m * 8 + j] = 0;
        asm volatile("fence.proxy.async.global;" ::: "memory");
        PROF(22);
        mbar_expect_tx(bars + 8 * (B_RECV + 1), 8 * 2048);
#pragma unroll 1
        for (int src = 0; src < 8; src++)
          asm volatile("cp.async.bulk.shared::cluster.global.mbarrier::complete_tx::bytes [%0], [%1], %2, [%3];" ::"r"(
                           sH + RECV_OFF + src * PART_BYTES + 16384),
                       "l"(rp + (size_t)src * PART_BYTES + 16384), "r"(2048), "r"(bars + 8 * (B_RECV + 1))
                       : "memory");
      }
    } else {
      const int tid = threadIdx.x - 64;
      if (is_ffn) {
        mbar_wait_long(bars + 8 * B_GO, 0);
        if (tid == 0)
          asm volatile("cp.async.bulk.prefetch.L2.global [%0], %1;" ::"l"(ssm_k + (size_t)blockIdx.x * 4 * SEQ), "r"(4 * SEQ * 2) : "memory");
        conv_make_u(tid, blockIdx.x, kin, vin, shift_k);
        named_bar(4, 64);
        if (tid == 0) {
          asm volatile("red.release.gpu.global.add.u32 [%0], 1;" ::"l"(&g_u_done) : "memory");
        }
        mbar_wait_long(bars + 8 * B_HFREE, 0);
      }
#pragma unroll 1
      for (int gi = 0; gi < ngrp; gi++) {
        conv_make_g(sH + gi * 4 * CONV_CH_BYTES, tid, (grp0 + gi) * 4, ssm_k, ssm_D);
        fence_async_smem();
        __syncwarp();
        if (lane == 0) mbar_arrive(bars + 8 * (B_TAB + gi));
      }
      if (tid == 0) {
        spin_ge(&g_u_done, 128);
        const unsigned int seen = atomicAdd(&g_u_seen, 1);
        asm volatile("fence.proxy.async;" ::: "memory");
#pragma unroll 1
        for (int gi = 0; gi < ngrp; gi++) {
          mbar_expect_tx(bars + 8 * (B_TAB + gi), 4 * 4096);
#pragma unroll 1
          for (int ch = 0; ch < 4; ch++)
            asm volatile("cp.async.bulk.shared::cluster.global.mbarrier::complete_tx::bytes [%0], [%1], %2, [%3];" ::"r"(
                             sH + (gi * 4 + ch) * CONV_CH_BYTES + 256),
                         "l"(g_us + (size_t)((grp0 + gi) * 4 + ch) * (SEQ / 8)), "r"(4096), "r"(bars + 8 * (B_TAB + gi))
                         : "memory");
        }
        if (seen == NCONV_CTA - 1) { g_u_seen = 0; g_u_done = 0; }
        if (is_ffn) {
          const uint8_t* rp = reinterpret_cast<const uint8_t*>(g_part) + (size_t)(m * 8 + j) * 8 * PART_BYTES;
          mbar_wait_long(bars + 8 * B_RFREE, 0);
          spin_ge(&g_flag[m * 8 + j], 8);
          g_flag[m * 8 + j] = 0;
          asm volatile("fence.proxy.async.global;" ::: "memory");
          PROF(23);
          mbar_expect_tx(bars + 8 * B_RECV, 8 * 16384);
#pragma unroll 1
          for (int src = 0; src < 8; src++)
            asm volatile("cp.async.bulk.shared::cluster.global.mbarrier::complete_tx::bytes [%0], [%1], %2, [%3];" ::"r"(
                             sH + RECV_OFF + src * PART_BYTES),
                         "l"(rp + (size_t)src * PART_BYTES), "r"(16384), "r"(bars + 8 * B_RECV)
                         : "memory");
        }
      }
    }
  } else {
    asm volatile("setmaxnreg.inc.sync.aligned.u32 224;\n");
    const int cw = warp - 4;
    const int wg = cw >> 2;
    const uint32_t sPriv = sH + cw * 2048;
    uint32_t a[128];
    float acc[64];
    const int fr = (lane & 7) + ((lane >> 3) & 1) * 8;
    const uint32_t frow = sPriv + fr * 128;
    if (is_ffn) {
      uint32_t m2a, m2b, rha, rla, rhb, rlb;
      {
        float sm[4] = {0.f, 0.f, 0.f, 0.f}, gl[4] = {0.f, 0.f, 0.f, 0.f}, gh[4] = {0.f, 0.f, 0.f, 0.f};
        float sm2[4] = {0.f, 0.f, 0.f, 0.f}, gl2[4] = {0.f, 0.f, 0.f, 0.f}, gh2[4] = {0.f, 0.f, 0.f, 0.f};
#pragma unroll 1
        for (int i3 = 0; i3 < 3; i3++) {
          mbar_wait(bars + 8 * (B_X + i3), 0);
          if (cw == 0 && i3 == 0) PROF(24);
          if (cw == 0 && i3 == 2) PROF(26);
#pragma unroll
          for (int ks = 0; ks < 12; ks += 2) {
            uint32_t r0, r1, r2, r3, u0, u1, u2, u3;
            const uint32_t tb = frow + (i3 * 3 + (ks >> 2)) * 16384;
            ldsm_x4(tb + (((2 * (ks & 3) + (lane >> 4)) ^ (fr & 7)) << 4), r0, r1, r2, r3);
            ldsm_x4(tb + (((2 * (ks & 3) + 2 + (lane >> 4)) ^ (fr & 7)) << 4), u0, u1, u2, u3);
            mma16816(sm, r0, r1, r2, r3, 0x3F803F80u, 0x3F803F80u);
            mma16816(gl, r0, r1, r2, r3, r0, r2);
            mma16816(gh, r0, r1, r2, r3, r1, r3);
            mma16816(sm2, u0, u1, u2, u3, 0x3F803F80u, 0x3F803F80u);
            mma16816(gl2, u0, u1, u2, u3, u0, u2);
            mma16816(gh2, u0, u1, u2, u3, u1, u3);
          }
        }
#pragma unroll
        for (int i = 0; i < 4; i++) { sm[i] += sm2[i]; gl[i] += gl2[i]; gh[i] += gh2[i]; }
        if (cw == 0) PROF(1);
        const int gg = lane >> 2, src = (lane & ~3) | (gg >> 1);
        const float qa = __shfl_sync(0xffffffffu, (gg & 1) ? gl[1] : gl[0], src);
        const float qb = __shfl_sync(0xffffffffu, (gg & 1) ? gh[3] : gh[2], src);
        const float ma = sm[0] * (1.0f / DM), mb = sm[2] * (1.0f / DM);
        float va = qa * (1.0f / DM) - ma * ma, vb = qb * (1.0f / DM) - mb * mb;
        if (__any_sync(0xffffffffu, !(ma * ma <= 32.f * va) || !(mb * mb <= 32.f * vb))) {
          float ca = 0.f, cb = 0.f;
#pragma unroll 1
          for (int ks = 0; ks < 36; ks++) {
            const int ch = 2 * (ks & 3) + (lane >> 4);
            uint32_t r0, r1, r2, r3;
            ldsm_x4(frow + (ks >> 2) * 16384 + ((ch ^ (fr & 7)) << 4), r0, r1, r2, r3);
            float d;
            d = bf_lo(r0) - ma; ca = fmaf(d, d, ca); d = bf_hi(r0) - ma; ca = fmaf(d, d, ca);
            d = bf_lo(r2) - ma; ca = fmaf(d, d, ca); d = bf_hi(r2) - ma; ca = fmaf(d, d, ca);
            d = bf_lo(r1) - mb; cb = fmaf(d, d, cb); d = bf_hi(r1) - mb; cb = fmaf(d, d, cb);
            d = bf_lo(r3) - mb; cb = fmaf(d, d, cb); d = bf_hi(r3) - mb; cb = fmaf(d, d, cb);
          }
          ca += __shfl_xor_sync(0xffffffffu, ca, 1); ca += __shfl_xor_sync(0xffffffffu, ca, 2);
          cb += __shfl_xor_sync(0xffffffffu, cb, 1); cb += __shfl_xor_sync(0xffffffffu, cb, 2);
          va = ca * (1.0f / DM); vb = cb * (1.0f / DM);
        }
        va = fmaxf(va, 0.f); vb = fmaxf(vb, 0.f);
        const float mua = rbf(ma), mub = rbf(mb);
        const float sda = rbf(fast_sqrt(rbf(rbf(va) + 1e-5f))), sdb = rbf(fast_sqrt(rbf(rbf(vb) + 1e-5f)));
        m2a = pack_bf16(mua, mua); m2b = pack_bf16(mub, mub);
        {
          const float ra = fast_rcp(sda), rb = fast_rcp(sdb);
          const float ha = rbf(ra), hb = rbf(rb);
          rha = pack_bf16(ha, ha); rhb = pack_bf16(hb, hb);
          rla = pack_bf16(ra - ha, ra - ha); rlb = pack_bf16(rb - hb, rb - hb);
        }
        if (cw == j && (lane & 3) == 0) {
          uint32_t* st = reinterpret_cast<uint32_t*>(smem + STATS_OFF);
          st[(lane >> 2) * 3] = m2a; st[(lane >> 2) * 3 + 1] = rha; st[(lane >> 2) * 3 + 2] = rla;
          st[24 + (lane >> 2) * 3] = m2b; st[24 + (lane >> 2) * 3 + 1] = rhb; st[24 + (lane >> 2) * 3 + 2] = rlb;
        }
      }
      if (cw == 0) PROF(2);
#pragma unroll
      for (int i = 0; i < 64; i++) asm volatile("mov.f32 %0, 0f00000000;" : "=f"(acc[i]));
      int s = 0;
      uint32_t ph = 0;
      const uint32_t bdesc0 = ((sST & 0x3FFFF) >> 4) | ((8192u >> 4) << 16);
      const uint32_t adesc8 = (((sH + 8 * 16384 + wg * 8192) & 0x3FFFF) >> 4) | (1u << 16);
      uint32_t hp[16];
      auto chunk = [&](auto mode_tag, int c) {
        constexpr bool FIRST = decltype(mode_tag)::value == 0, LAST = decltype(mode_tag)::value == 2;
        int sprev = 0;
#pragma unroll
        for (int kb = 0; kb < 9; kb++) {
          mbar_wait(bars + 8 * (B_FULL + s), ph);
          if (FIRST && kb < 8) {
#pragma unroll
            for (int kk = 0; kk < 4; kk++) {
              const int ch = 2 * kk + (lane >> 4);
              ldsm_x4(frow + kb * 16384 + ((ch ^ (fr & 7)) << 4), a[kb * 16 + kk * 4 + 0], a[kb * 16 + kk * 4 + 1],
                      a[kb * 16 + kk * 4 + 2], a[kb * 16 + kk * 4 + 3]);
            }
#pragma unroll
            for (int i = 0; i < 16; i++) ln_apply(a[kb * 16 + i], (i & 1) ? m2b : m2a, (i & 1) ? rhb : rha, (i & 1) ? rlb : rla);
          }
          if (FIRST && kb == 8) named_bar(1 + wg, 128);
          wg_fence();
          const uint32_t dsc = bdesc0 + s * (STAGE_BYTES >> 4);
#pragma unroll
          for (int kk = 0; kk < 4; kk++) {
            if (kb == 0 && kk == 0)
              wgmma_rs128_first(acc, a[0], a[1], a[2], a[3], dsc);
            else if (kb < 8)
              wgmma_rs128(acc, a[kb * 16 + kk * 4 + 0], a[kb * 16 + kk * 4 + 1], a[kb * 16 + kk * 4 + 2], a[kb * 16 + kk * 4 + 3],
                          dsc + kk * 128);
            else
              wgmma_ss128(acc, adesc8 + kk * 2, dsc + kk * 128);
          }
          wg_commit();
          if (!FIRST && kb == 0) {
#pragma unroll
            for (int i = 0; i < 4; i++)
              sts_v4(sPriv + (c - 1) * 16384 + i * 512 + lane * 16, hp[i * 4], hp[i * 4 + 1], hp[i * 4 + 2], hp[i * 4 + 3]);
          }
          if (FIRST && kb == 1) {
#pragma unroll
            for (int kk = 0; kk < 4; kk++) {
              const int ch = 2 * kk + (lane >> 4);
              ldsm_x4(frow + 8 * 16384 + ((ch ^ (fr & 7)) << 4), hp[kk * 4 + 0], hp[kk * 4 + 1], hp[kk * 4 + 2], hp[kk * 4 + 3]);
            }
#pragma unroll
            for (int i = 0; i < 16; i++) ln_apply(hp[i], (i & 1) ? m2b : m2a, (i & 1) ? rhb : rha, (i & 1) ? rlb : rla);
#pragma unroll
            for (int kk = 0; kk < 4; kk++) {
              const int ch = 2 * kk + (lane >> 4);
              stsm_x4(frow + 8 * 16384 + ((ch ^ (fr & 7)) << 4), hp[kk * 4 + 0], hp[kk * 4 + 1], hp[kk * 4 + 2], hp[kk * 4 + 3]);
            }
            fence_async_smem();
          }
          if (kb > 0) {
            wg_wait<1>();
            if (lane == 0) mbar_arrive(bars + 8 * (B_EMPTY + sprev));
            if (LAST) {
#pragma unroll
              for (int i = 0; i < 4; i++)
                lds_v4(sPriv + (kb - 1) * 16384 + i * 512 + lane * 16, a[(kb - 1) * 16 + i * 4 + 0], a[(kb - 1) * 16 + i * 4 + 1],
                       a[(kb - 1) * 16 + i * 4 + 2], a[(kb - 1) * 16 + i * 4 + 3]);
            }
          }
          sprev = s;
          if (++s == NST) { s = 0; ph ^= 1; }
        }
        wg_wait<0>();
        acc_fence(acc);
        if (lane == 0) mbar_arrive(bars + 8 * (B_EMPTY + sprev));
        if (LAST) {
          __syncwarp();
          if (lane == 0) mbar_arrive(bars + 8 * B_HFREE);
          named_bar(1 + wg, 128);
        }
#pragma unroll
        for (int i = 0; i < 16; i++) {
          const int jt = (i >> 2) * 2 + ((i >> 1) & 1), hh = i & 1;
          const uint32_t g = pack_bf16_relu(acc[jt * 4 + hh * 2], acc[jt * 4 + hh * 2 + 1]);
          const uint32_t u = pack_bf16(acc[32 + jt * 4 + hh * 2], acc[32 + jt * 4 + hh * 2 + 1]);
          hp[i] = mul_bf16x2(g, u);
        }
        if (LAST) {
#pragma unroll
          for (int i = 0; i < 4; i++) {
            const int ch = 2 * i + (lane >> 4);
            stsm_x4(frow + 8 * 16384 + ((ch ^ (fr & 7)) << 4), hp[i * 4], hp[i * 4 + 1], hp[i * 4 + 2], hp[i * 4 + 3]);
          }
        }
        if (LAST) {
          fence_async_smem();
          named_bar(1 + wg, 128);
        }
      };
      chunk(std::integral_constant<int, 0>{}, 0);
      if (lane == 0) mbar_arrive(bars + 8 * B_GO);
      if (cw == 0) PROF(30);
      for (int c = 1; c < 8; c++) { chunk(std::integral_constant<int, 1>{}, c); if (cw == 0 && c == 4) PROF(31); }
      chunk(std::integral_constant<int, 2>{}, 8);
      if (cw == 0) PROF(3);
      auto stage_out = [&](int p, int nsub) {
        if (p > 0) mbar_wait(bars + 8 * B_SFREE, (p - 1) & 1);
#pragma unroll
        for (int sb = 0; sb < 2; sb++) {
          if (sb < nsub) {
#pragma unroll
            for (int q = 0; q < 4; q++) {
              const int jt = sb * 8 + q * 2;
              const int ch = q * 2 + (lane >> 4);
              stsm_x4(frow + STG_OFF + sb * 16384 + ((ch ^ (fr & 7)) << 4), pack_bf16(acc[jt * 4 + 0], acc[jt * 4 + 1]),
                      pack_bf16(acc[jt * 4 + 2], acc[jt * 4 + 3]), pack_bf16(acc[jt * 4 + 4], acc[jt * 4 + 5]),
                      pack_bf16(acc[jt * 4 + 6], acc[jt * 4 + 7]));
            }
          }
        }
      };
      auto stage_signal = [&]() {
        fence_async_smem();
        __syncwarp();
        if (lane == 0) mbar_arrive(bars + 8 * B_STAGED);
      };
#pragma unroll 1
      for (int p = 0; p < 4; p++) {
        int sprev = 0;
#pragma unroll
        for (int kb = 0; kb < 9; kb++) {
          mbar_wait(bars + 8 * (B_FULL + s), ph);
          wg_fence();
          const uint32_t dsc = bdesc0 + s * (STAGE_BYTES >> 4);
#pragma unroll
          for (int kk = 0; kk < 4; kk++) {
            if (kb == 0 && kk == 0)
              wgmma_rs128_first(acc, a[0], a[1], a[2], a[3], dsc);
            else if (kb < 8)
              wgmma_rs128(acc, a[kb * 16 + kk * 4 + 0], a[kb * 16 + kk * 4 + 1], a[kb * 16 + kk * 4 + 2], a[kb * 16 + kk * 4 + 3],
                          dsc + kk * 128);
            else
              wgmma_ss128(acc, adesc8 + kk * 2, dsc + kk * 128);
          }
          wg_commit();
          if (kb == 0 && p > 0) stage_signal();
          if (kb > 0) {
            wg_wait<1>();
            if (lane == 0) mbar_arrive(bars + 8 * (B_EMPTY + sprev));
          }
          sprev = s;
          if (++s == NST) { s = 0; ph ^= 1; }
        }
        wg_wait<0>();
        acc_fence(acc);
        if (lane == 0) mbar_arrive(bars + 8 * (B_EMPTY + sprev));
        stage_out(p, 2);
        if (cw == 0) PROF(8 + p);
      }
      {
        int sprev = 0;
#pragma unroll
        for (int kp = 0; kp < 5; kp++) {
          mbar_wait(bars + 8 * (B_FULL + s), ph);
          wg_fence();
          const uint32_t dsc = bdesc0 + s * (STAGE_BYTES >> 4);
#pragma unroll
          for (int kk = 0; kk < 8; kk++) {
            if (kp < 4) {
              const int ai = kp * 32 + kk * 4;
              if (kp == 0 && kk == 0) wgmma_rs64_first(acc, a[0], a[1], a[2], a[3], dsc);
              else wgmma_rs64(acc, a[ai], a[ai + 1], a[ai + 2], a[ai + 3], dsc + (kk >> 2) * 512 + (kk & 3) * 128);
            } else if (kk < 4) {
              wgmma_ss64(acc, adesc8 + kk * 2, dsc + kk * 128);
            }
          }
          wg_commit();
          if (kp == 0) stage_signal();
          if (kp > 0) {
            wg_wait<1>();
            if (lane == 0) mbar_arrive(bars + 8 * (B_EMPTY + sprev));
          }
          sprev = s;
          if (++s == NST) { s = 0; ph ^= 1; }
        }
        wg_wait<0>();
        acc_fence(acc);
        stage_out(4, 1);
        stage_signal();
      }
      if (cw == 0) PROF(4);
    }
#pragma unroll 1
    for (int gi = 0; gi < ngrp; gi++) {
      mbar_wait_long(bars + 8 * (B_TAB + gi), 0);
#pragma unroll 1
      for (int c = 0; c < 2; c++) {
        const int ch = wg * 2 + c, d = (grp0 + gi) * 4 + ch;
        conv_channel(acc, sH + (gi * 4 + ch) * CONV_CH_BYTES, sH + (is_ffn ? CONV_X_OFF : CONV_X_OFF_SP) + wg * 8192,
                     sH + (is_ffn ? CONV_Z_OFF : CONV_Z_OFF_SP) + wg * 4096, cw & 3, lane, 1 + wg, d,
                     cw == 0 ? 12 + 3 * c : 0);
      }
    }
    if (cw == 0) PROF(5);
    if (is_ffn) {
      const int t0 = m * 128 + j * 16;
      const int g = lane >> 2, q = lane & 3;
      const uint32_t xs = sH + cw * 6912, bsm = xs + 2304, zs = xs + 4608;
      named_bar(3, 256);
      if (cw == 0) PROF(18);
      {
        const uint8_t* xg = reinterpret_cast<const uint8_t*>(x + (size_t)t0 * DM + cw * 72);
#pragma unroll 1
        for (int idx = lane; idx < 144; idx += 32) {
          const int row = idx / 9, ch = idx - row * 9;
          asm volatile("cp.async.cg.shared.global [%0], [%1], 16;" ::"r"(xs + idx * 16), "l"(xg + row * (DM * 2) + ch * 16) : "memory");
        }
        asm volatile("cp.async.commit_group;" ::: "memory");
      }
      const int rr = (lane & 7) + ((lane >> 3) & 1) * 8;
      {
        const uint32_t ident = (g == 2 * q ? 0x3F80u : 0u) | (g == 2 * q + 1 ? 0x3F800000u : 0u);
        const uint32_t rbase = sH + RECV_OFF + (lane >> 4) * PART_BYTES + rr * 128;
        mbar_wait(bars + 8 * B_RECV, 0);
        if (cw == 7) mbar_wait(bars + 8 * (B_RECV + 1), 0);
        if (cw == 0) PROF(25);
#pragma unroll 3
        for (int i = 0; i < 9; i++) {
          const int c8 = cw * 9 + i;
          const uint32_t ad = rbase + (c8 >> 3) * 2048 + (((c8 & 7) ^ (rr & 7)) << 4);
          float d0 = 0.f, d1 = 0.f, d2 = 0.f, d3 = 0.f;
#pragma unroll
          for (int sp = 0; sp < 4; sp++) {
            uint32_t r0, r1, r2, r3;
            ldsm_x4(ad + sp * 2 * PART_BYTES, r0, r1, r2, r3);
            asm volatile("mma.sync.aligned.m16n8k16.row.col.f32.bf16.bf16.f32 {%0,%1,%2,%3}, {%4,%5,%6,%7}, {%8,%8}, {%0,%1,%2,%3};"
                         : "+f"(d0), "+f"(d1), "+f"(d2), "+f"(d3) : "r"(r0), "r"(r1), "r"(r2), "r"(r3), "r"(ident));
          }
          asm volatile("st.shared.v2.b32 [%0], {%1, %2};" ::"r"(bsm + i * 256 + lane * 8), "r"(pack_bf16(d0, d1)), "r"(pack_bf16(d2, d3))
                       : "memory");
        }
      }
      if (cw == 0) PROF(6);
      {
        uint4* zp = g_z + (m * 8 + j) * (DM * 2) + cw * 144;
        {
          uint4 zv[5];
          int tries = 0;
          bool ok;
          do {
            ok = true;
#pragma unroll
            for (int i = 0; i < 5; i++) {
              const int idx = i * 32 + lane;
              if (idx < 144) {
                asm volatile("ld.relaxed.gpu.global.v4.u32 {%0, %1, %2, %3}, [%4];"
                             : "=r"(zv[i].x), "=r"(zv[i].y), "=r"(zv[i].z), "=r"(zv[i].w)
                             : "l"(zp + idx) : "memory");
              }
            }
#pragma unroll
            for (int i = 0; i < 5; i++)
              if (i * 32 + lane < 144) ok = ok && zv[i].x && zv[i].y && zv[i].z && zv[i].w;
          } while (!__all_sync(0xffffffffu, ok) && ++tries < (1 << 20));
#pragma unroll
          for (int i = 0; i < 5; i++) {
            const int idx = i * 32 + lane, row = idx >> 1;
            if (idx < 144) {
              sts_v4(zs + row * 32 + (((idx & 1) ^ ((row >> 2) & 1)) << 4), ~zv[i].x, ~zv[i].y, ~zv[i].z, ~zv[i].w);
              __stcg(zp + idx, make_uint4(0u, 0u, 0u, 0u));
            }
          }
        }
        if (cw == 0) PROF(28);
        asm volatile("cp.async.wait_group 0;" ::: "memory");
        __syncwarp();
      }
      if (cw == 0) PROF(29);
      const uint32_t* st = reinterpret_cast<const uint32_t*>(smem + STATS_OFF);
      const uint32_t mu2a = st[g * 3], fha = st[g * 3 + 1], fla = st[g * 3 + 2];
      const uint32_t mu2b = st[24 + g * 3], fhb = st[24 + g * 3 + 1], flb = st[24 + g * 3 + 2];
#pragma unroll 3
      for (int i = 0; i < 9; i++) {
        uint32_t z0, z1, x0, x1, b0, b1;
        const int zr = i * 8 + (lane & 7), hf = (lane >> 3) & 1;
        asm volatile("ldmatrix.sync.aligned.m8n8.x2.trans.shared.b16 {%0, %1}, [%2];" : "=r"(z0), "=r"(z1)
                     : "r"(zs + zr * 32 + ((hf ^ ((zr >> 2) & 1)) << 4)) : "memory");
        asm volatile("ldmatrix.sync.aligned.m8n8.x2.shared.b16 {%0, %1}, [%2];" : "=r"(x0), "=r"(x1) : "r"(xs + rr * 144 + i * 16) : "memory");
        asm volatile("ld.shared.v2.b32 {%0, %1}, [%2];" : "=r"(b0), "=r"(b1) : "r"(bsm + i * 256 + lane * 8) : "memory");
        uint32_t n0 = x0, n1 = x1;
        ln_apply(n0, mu2a, fha, fla);
        ln_apply(n1, mu2b, fhb, flb);
        const uint32_t o0 = add_bf16x2(add_bf16x2(x0, mul_bf16x2(n0, z0)), b0);
        const uint32_t o1 = add_bf16x2(add_bf16x2(x1, mul_bf16x2(n1, z1)), b1);
        asm volatile("stmatrix.sync.aligned.m8n8.x2.shared.b16 [%0], {%1, %2};" ::"r"(xs + rr * 144 + i * 16), "r"(o0), "r"(o1) : "memory");
      }
      __syncwarp();
      {
        uint8_t* og = reinterpret_cast<uint8_t*>(out + (size_t)t0 * DM + cw * 72);
#pragma unroll 1
        for (int idx = lane; idx < 144; idx += 32) {
          const int row = idx / 9, ch = idx - row * 9;
          uint32_t a0, a1, a2, a3;
          lds_v4(xs + idx * 16, a0, a1, a2, a3);
          *reinterpret_cast<uint4*>(og + row * (DM * 2) + ch * 16) = make_uint4(a0, a1, a2, a3);
        }
      }
      if (cw == 0) PROF(7);
    }
  }
}

typedef CUresult (*EncodeTiledFn)(CUtensorMap*, CUtensorMapDataType, cuuint32_t, void*, const cuuint64_t*, const cuuint64_t*,
                                  const cuuint32_t*, const cuuint32_t*, CUtensorMapInterleave, CUtensorMapSwizzle,
                                  CUtensorMapL2promotion, CUtensorMapFloatOOBfill);

CUtensorMap make_map(EncodeTiledFn fn, const void* base, uint64_t inner, uint64_t outer, uint32_t bi, uint32_t bo) {
  CUtensorMap mp;
  cuuint64_t dims[2] = {inner, outer};
  cuuint64_t strides[1] = {inner * 2};
  cuuint32_t box[2] = {bi, bo};
  cuuint32_t es[2] = {1, 1};
  fn(&mp, CU_TENSOR_MAP_DATA_TYPE_BFLOAT16, 2, const_cast<void*>(base), dims, strides, box, es, CU_TENSOR_MAP_INTERLEAVE_NONE,
     CU_TENSOR_MAP_SWIZZLE_128B, CU_TENSOR_MAP_L2_PROMOTION_L2_128B, CU_TENSOR_MAP_FLOAT_OOB_FILL_NONE);
  return mp;
}

CUtensorMap make_map_x(EncodeTiledFn fn, const void* base) {
  CUtensorMap mp;
  cuuint64_t dims[3] = {64, (cuuint64_t)SEQ, 9};
  cuuint64_t strides[2] = {(cuuint64_t)DM * 2, 128};
  cuuint32_t box[3] = {64, 128, 3};
  cuuint32_t es[3] = {1, 1, 1};
  fn(&mp, CU_TENSOR_MAP_DATA_TYPE_BFLOAT16, 3, const_cast<void*>(base), dims, strides, box, es, CU_TENSOR_MAP_INTERLEAVE_NONE,
     CU_TENSOR_MAP_SWIZZLE_128B, CU_TENSOR_MAP_L2_PROMOTION_L2_128B, CU_TENSOR_MAP_FLOAT_OOB_FILL_NONE);
  return mp;
}

}

extern "C" void kernel_launch(void* const* d_in, const int* in_sizes, int n_in, void* d_out, int out_size) {
  const bf16* q = (const bf16*)d_in[0];
  const bf16* k = (const bf16*)d_in[1];
  const bf16* v = (const bf16*)d_in[2];
  const bf16* shift_k = (const bf16*)d_in[3];
  const bf16* ssm_k = (const bf16*)d_in[4];
  const bf16* ssm_D = (const bf16*)d_in[5];
  const bf16* wg = (const bf16*)d_in[7];
  const bf16* wu = (const bf16*)d_in[8];
  const bf16* wd = (const bf16*)d_in[9];
  bf16* out = (bf16*)d_out;

  static EncodeTiledFn fn = nullptr;
  if (!fn) {
    void* p = nullptr;
    cudaDriverEntryPointQueryResult qr;
    cudaGetDriverEntryPoint("cuTensorMapEncodeTiled", &p, cudaEnableDefault, &qr);
    fn = (EncodeTiledFn)p;
    cudaFuncSetAttribute(fused_kernel, cudaFuncAttributeMaxDynamicSharedMemorySize, SMEM_BYTES);
  }
  const CUtensorMap mx = make_map_x(fn, q);
  const CUtensorMap mg = make_map(fn, wg, FF, DM, 64, 64);
  const CUtensorMap mu = make_map(fn, wu, FF, DM, 64, 64);
  const CUtensorMap md = make_map(fn, wd, DM, FF, 64, 64);
  fused_kernel<<<NCONV_CTA, 384, SMEM_BYTES, cudaStreamPerThread>>>(mx, mg, mu, md, q, k, v, shift_k, ssm_k, ssm_D, out);
}
```
